```python
import torch

def _softmax(x, axis=-1):
    return torch.softmax(x, dim=axis)
def _gelu(x):
    return torch.nn.functional.gelu(x, approximate="tanh")
def _silu(x):
    return torch.nn.functional.silu(x)
def _sigmoid(x):
    return torch.sigmoid(x)
def _layernorm(x, axis=-1, eps=1e-5):
    m = x.mean(dim=axis, keepdim=True)
    v = x.var(dim=axis, keepdim=True, unbiased=False)
    return (x - m) / torch.sqrt(v + eps)
def _scatter_add(tgt, idx, src, axis=0):
    return tgt.clone().index_add_(axis, idx, src)
def _segment_sum(src, seg, n):
    out = torch.zeros((n,) + src.shape[1:], dtype=src.dtype)
    return out.index_add_(0, seg, src)
def _pad(x, pw):
    flat = tuple(v for pair in reversed(pw) for v in pair)
    return torch.nn.functional.pad(x, flat)

kernel_name = 'concat_heads__gqa_block_cached__mha_block_cached__near_ridge'

def setup_inputs():

    _w = (lambda a: (lambda t: t.to(torch.bfloat16) if t.is_floating_point() else t)(torch.as_tensor(a)))
    def _A_setup():
        B, Sq, D = 16, 144, 512
        Hq, Hkv, Sk, Dh = 32, 32, 512, 128
        assert Hq % Hkv == 0, (Hq, Hkv)
        return {
            "x": _w((lambda *s: torch.randn(*s, dtype=torch.bfloat16) * 0.8)(B, Sq, D)),
            "k_cache": _w((lambda *s: torch.randn(*s, dtype=torch.bfloat16) * 0.8)(B, Hkv, Sk, Dh)),
            "v_cache": _w((lambda *s: torch.randn(*s, dtype=torch.bfloat16) * 0.05)(B, Hkv, Sk, Dh)),
            "wq": _w((lambda *s: torch.randn(*s, dtype=torch.bfloat16) * 0.8)(D, Hq * Dh) * (D ** -0.5)),
            "wo": _w((lambda *s: torch.randn(*s, dtype=torch.bfloat16) * 0.05)(Hq * Dh, D) * ((Hq * Dh) ** -0.5)),
        }
    _A_in = _A_setup()

    def _B_setup():
        B, Sq, D = 16, 144, 512
        H, Sk, Dh = 32, 512, 128
        return {
            "x": _w((lambda *s: torch.randn(*s, dtype=torch.bfloat16) * 0.8)(B, Sq, D)),
            "k_cache": _w((lambda *s: torch.randn(*s, dtype=torch.bfloat16) * 0.8)(B, H, Sk, Dh)),
            "v_cache": _w((lambda *s: torch.randn(*s, dtype=torch.bfloat16) * 0.05)(B, H, Sk, Dh)),
            "wq": _w((lambda *s: torch.randn(*s, dtype=torch.bfloat16) * 0.8)(D, H * Dh) * (D ** -0.5)),
            "wo": _w((lambda *s: torch.randn(*s, dtype=torch.bfloat16) * 0.05)(H * Dh, D) * ((H * Dh) ** -0.5)),
        }
    _B_in = _B_setup()

    return {
        "A_x": _A_in["x"],
        "A_k_cache": _A_in["k_cache"],
        "A_v_cache": _A_in["v_cache"],
        "A_wq": _A_in["wq"],
        "A_wo": _A_in["wo"],
        "B_x": _B_in["x"],
        "B_k_cache": _B_in["k_cache"],
        "B_v_cache": _B_in["v_cache"],
        "B_wq": _B_in["wq"],
        "B_wo": _B_in["wo"],
    }

def reference(A_x, A_k_cache, A_v_cache, A_wq, A_wo, B_x, B_k_cache, B_v_cache, B_wq, B_wo):
    def _A_ref(x, k_cache, v_cache, wq, wo):
        B, Sq, D = x.shape
        Hq, Dh = 32, 128
        Hkv = k_cache.shape[1]
        rep = Hq // Hkv
        q = (lambda x, *d: x.permute(*d))((x @ wq).reshape(B, Sq, Hq, Dh), 0, 2, 1, 3)
        k = (lambda x, n, axis: torch.repeat_interleave(x, n, dim=axis))(k_cache, rep, axis=1)
        v = (lambda x, n, axis: torch.repeat_interleave(x, n, dim=axis))(v_cache, rep, axis=1)
        scores = torch.einsum("bhqd,bhkd->bhqk", q, k) * (Dh ** -0.5)
        p = _softmax(scores, axis=-1)
        o = torch.einsum("bhqk,bhkd->bhqd", p, v)
        return (lambda x, *d: x.permute(*d))(o, 0, 2, 1, 3).reshape(B, Sq, Hq * Dh) @ wo

    def _B_ref(x, k_cache, v_cache, wq, wo):
        B, Sq, D = x.shape
        H, Dh = 32, 128
        q = (lambda x, *d: x.permute(*d))((x @ wq).reshape(B, Sq, H, Dh), 0, 2, 1, 3)
        scores = torch.einsum("bhqd,bhkd->bhqk", q, k_cache) * (Dh ** -0.5)
        p = _softmax(scores, axis=-1)
        o = torch.einsum("bhqk,bhkd->bhqd", p, v_cache)
        return (lambda x, *d: x.permute(*d))(o, 0, 2, 1, 3).reshape(B, Sq, H * Dh) @ wo

    a = _A_ref(A_x, A_k_cache, A_v_cache, A_wq, A_wo)
    b = _B_ref(B_x, B_k_cache, B_v_cache, B_wq, B_wo)
    return torch.concatenate([a, b], axis=-1)
```

```cpp
#include <cuda_runtime.h>
#include <cuda_bf16.h>
#include <cuda.h>
#include <stdint.h>

namespace {

constexpr int NQ = 144;
constexpr int NB = 16;
constexpr int NH = 32;
constexpr int SK = 512;
constexpr int DM = 512;
constexpr int HD = 4096;
constexpr int NROWS = NB * NQ;
constexpr int TILE_B = NQ * 128;
constexpr int NSLOT = 5;
constexpr int XW_BYTES = TILE_B + 16384;

constexpr int SLOT_B = 34816;
constexpr int OFF_Q = 0;
constexpr int OFF_RING = OFF_Q + 2 * TILE_B;
constexpr int OFF_PR = OFF_RING + NSLOT * SLOT_B;
constexpr int OFF_RD = OFF_PR + 2048;
constexpr int OFF_BAR = OFF_RD + 256;
constexpr int SMEM_A = OFF_BAR + 256;

constexpr int OP_STAGES = 5;
constexpr int SMEM_B = OP_STAGES * XW_BYTES + 2 * TILE_B + 256;

__device__ __nv_bfloat16 g_oscratch[2 * NROWS * HD];

template <int V> struct IC { static constexpr int value = V; };
#define TS(k)
struct Maps {
  CUtensorMap x[2], wq[2], k[2], v[2], wo[2], os[2], out;
};

__device__ __forceinline__ uint32_t smem_u32(const void* p) {
  return (uint32_t)__cvta_generic_to_shared(p);
}
__device__ __forceinline__ void mbar_init(uint32_t bar, uint32_t cnt) {
  asm volatile("mbarrier.init.shared::cta.b64 [%0], %1;" ::"r"(bar), "r"(cnt));
}
__device__ __forceinline__ void mbar_expect_tx(uint32_t bar, uint32_t bytes) {
  asm volatile("mbarrier.arrive.expect_tx.shared::cta.b64 _, [%0], %1;" ::"r"(bar), "r"(bytes) : "memory");
}
__device__ __forceinline__ void mbar_arrive(uint32_t bar) {
  asm volatile("mbarrier.arrive.shared::cta.b64 _, [%0];" ::"r"(bar) : "memory");
}
__device__ __forceinline__ void mbar_arrive_cnt(uint32_t bar, uint32_t c) {
  asm volatile("mbarrier.arrive.shared::cta.b64 _, [%0], %1;" ::"r"(bar), "r"(c) : "memory");
}
__device__ __forceinline__ void mbar_wait(uint32_t bar, uint32_t parity) {
  uint32_t ok;
  for (uint32_t it = 0;; it++) {
    asm volatile("{\n.reg .pred p;\nmbarrier.try_wait.parity.shared::cta.b64 p, [%1], %2;\nselp.u32 %0, 1, 0, p;\n}\n"
                 : "=r"(ok) : "r"(bar), "r"(parity) : "memory");
    if (ok) break;
    if (it > 40000000u) break;
  }
}
__device__ __forceinline__ void tma_load_2d(uint32_t dst, const CUtensorMap* map, int c0, int c1, uint32_t bar) {
  asm volatile(
      "cp.async.bulk.tensor.2d.shared::cluster.global.mbarrier::complete_tx::bytes [%0], [%1, {%3, %4}], [%2];"
      ::"r"(dst), "l"((uint64_t)map), "r"(bar), "r"(c0), "r"(c1) : "memory");
}
__device__ __forceinline__ void tma_store_2d(const CUtensorMap* map, uint32_t src, int c0, int c1) {
  asm volatile("cp.async.bulk.tensor.2d.global.shared::cta.bulk_group [%0, {%2, %3}], [%1];"
               ::"l"((uint64_t)map), "r"(src), "r"(c0), "r"(c1) : "memory");
}
__device__ __forceinline__ void bar_sync(int id, int n) { asm volatile("bar.sync %0, %1;" ::"r"(id), "r"(n) : "memory"); }
__device__ __forceinline__ void bar_arrive(int id, int n) { asm volatile("bar.arrive %0, %1;" ::"r"(id), "r"(n) : "memory"); }
__device__ __forceinline__ void fence_async() { asm volatile("fence.proxy.async.shared::cta;" ::: "memory"); }
__device__ __forceinline__ void wg_fence() { asm volatile("wgmma.fence.sync.aligned;" ::: "memory"); }
__device__ __forceinline__ void wg_commit() { asm volatile("wgmma.commit_group.sync.aligned;" ::: "memory"); }
template <int N>
__device__ __forceinline__ void wg_wait() { asm volatile("wgmma.wait_group.sync.aligned %0;" ::"n"(N) : "memory"); }

__device__ __forceinline__ uint64_t make_desc(uint32_t addr) {
  return (uint64_t)((addr & 0x3FFFF) >> 4) | ((uint64_t)1 << 16) | ((uint64_t)64 << 32) | ((uint64_t)1 << 62);
}

#define ACC_LIST(d)                                                                                        \
  "+f"(d[0]), "+f"(d[1]), "+f"(d[2]), "+f"(d[3]), "+f"(d[4]), "+f"(d[5]), "+f"(d[6]), "+f"(d[7]),          \
  "+f"(d[8]), "+f"(d[9]), "+f"(d[10]), "+f"(d[11]), "+f"(d[12]), "+f"(d[13]), "+f"(d[14]), "+f"(d[15]),    \
  "+f"(d[16]), "+f"(d[17]), "+f"(d[18]), "+f"(d[19]), "+f"(d[20]), "+f"(d[21]), "+f"(d[22]), "+f"(d[23]),  \
  "+f"(d[24]), "+f"(d[25]), "+f"(d[26]), "+f"(d[27]), "+f"(d[28]), "+f"(d[29]), "+f"(d[30]), "+f"(d[31]),  \
  "+f"(d[32]), "+f"(d[33]), "+f"(d[34]), "+f"(d[35]), "+f"(d[36]), "+f"(d[37]), "+f"(d[38]), "+f"(d[39]),  \
  "+f"(d[40]), "+f"(d[41]), "+f"(d[42]), "+f"(d[43]), "+f"(d[44]), "+f"(d[45]), "+f"(d[46]), "+f"(d[47]),  \
  "+f"(d[48]), "+f"(d[49]), "+f"(d[50]), "+f"(d[51]), "+f"(d[52]), "+f"(d[53]), "+f"(d[54]), "+f"(d[55]),  \
  "+f"(d[56]), "+f"(d[57]), "+f"(d[58]), "+f"(d[59]), "+f"(d[60]), "+f"(d[61]), "+f"(d[62]), "+f"(d[63]),  \
  "+f"(d[64]), "+f"(d[65]), "+f"(d[66]), "+f"(d[67]), "+f"(d[68]), "+f"(d[69]), "+f"(d[70]), "+f"(d[71])

#define REGS72 "{%0, %1, %2, %3, %4, %5, %6, %7, %8, %9, %10, %11, %12, %13, %14, %15, %16, %17, %18, %19, %20, %21, %22, %23, %24, %25, %26, %27, %28, %29, %30, %31, %32, %33, %34, %35, %36, %37, %38, %39, %40, %41, %42, %43, %44, %45, %46, %47, %48, %49, %50, %51, %52, %53, %54, %55, %56, %57, %58, %59, %60, %61, %62, %63, %64, %65, %66, %67, %68, %69, %70, %71}"
template <int TRANS_A>
__device__ __forceinline__ void wgmma144(float (&d)[72], uint64_t da, uint64_t db) {
  asm volatile("wgmma.mma_async.sync.aligned.m64n144k16.f32.bf16.bf16 " REGS72 ", %72, %73, 1, 1, 1, %74, 0;\n"
      : ACC_LIST(d) : "l"(da), "l"(db), "n"(TRANS_A));
}
template <int TRANS_A>
__device__ __forceinline__ void wgmma144_0(float (&d)[72], uint64_t da, uint64_t db) {
  asm volatile("wgmma.mma_async.sync.aligned.m64n144k16.f32.bf16.bf16 " REGS72 ", %72, %73, 0, 1, 1, %74, 0;\n"
      : "=f"(d[0]), "=f"(d[1]), "=f"(d[2]), "=f"(d[3]), "=f"(d[4]), "=f"(d[5]), "=f"(d[6]), "=f"(d[7]), "=f"(d[8]), "=f"(d[9]), "=f"(d[10]), "=f"(d[11]), "=f"(d[12]), "=f"(d[13]), "=f"(d[14]), "=f"(d[15]), "=f"(d[16]), "=f"(d[17]), "=f"(d[18]), "=f"(d[19]), "=f"(d[20]), "=f"(d[21]), "=f"(d[22]), "=f"(d[23]), "=f"(d[24]), "=f"(d[25]), "=f"(d[26]), "=f"(d[27]), "=f"(d[28]), "=f"(d[29]), "=f"(d[30]), "=f"(d[31]), "=f"(d[32]), "=f"(d[33]), "=f"(d[34]), "=f"(d[35]), "=f"(d[36]), "=f"(d[37]), "=f"(d[38]), "=f"(d[39]), "=f"(d[40]), "=f"(d[41]), "=f"(d[42]), "=f"(d[43]), "=f"(d[44]), "=f"(d[45]), "=f"(d[46]), "=f"(d[47]), "=f"(d[48]), "=f"(d[49]), "=f"(d[50]), "=f"(d[51]), "=f"(d[52]), "=f"(d[53]), "=f"(d[54]), "=f"(d[55]), "=f"(d[56]), "=f"(d[57]), "=f"(d[58]), "=f"(d[59]), "=f"(d[60]), "=f"(d[61]), "=f"(d[62]), "=f"(d[63]), "=f"(d[64]), "=f"(d[65]), "=f"(d[66]), "=f"(d[67]), "=f"(d[68]), "=f"(d[69]), "=f"(d[70]), "=f"(d[71]) : "l"(da), "l"(db), "n"(TRANS_A));
}

__device__ __forceinline__ uint32_t pack_bf16(float lo, float hi) {
  uint32_t r;
  asm("cvt.rn.bf16x2.f32 %0, %1, %2;" : "=r"(r) : "f"(hi), "f"(lo));
  return r;
}
__device__ __forceinline__ void stmatrix_x4_t(uint32_t addr, uint32_t r0, uint32_t r1, uint32_t r2, uint32_t r3) {
  asm volatile("stmatrix.sync.aligned.m8n8.x4.trans.shared.b16 [%0], {%1, %2, %3, %4};"
               ::"r"(addr), "r"(r0), "r"(r1), "r"(r2), "r"(r3) : "memory");
}
__device__ __forceinline__ float ex2(float x) {
  float y;
  asm("ex2.approx.ftz.f32 %0, %1;" : "=f"(y) : "f"(x));
  return y;
}

__device__ __forceinline__ void store_acc_T(const float (&a)[72], uint32_t tile, int warp, int lane) {
  const int i = lane >> 3, r = lane & 7;
  const int chunk = (2 * warp + (i & 1)) ^ r;
  uint32_t addr = tile + (uint32_t)((8 * (i >> 1) + r) * 128 + chunk * 16);
#pragma unroll
  for (int j = 0; j < 18; j += 2) {
    stmatrix_x4_t(addr + j * 1024, pack_bf16(a[4 * j + 0], a[4 * j + 1]), pack_bf16(a[4 * j + 2], a[4 * j + 3]),
                  pack_bf16(a[4 * j + 4], a[4 * j + 5]), pack_bf16(a[4 * j + 6], a[4 * j + 7]));
  }
}

__device__ __forceinline__ void wgmma64_ss(float (&d)[32], uint64_t da, uint64_t db) {
  asm volatile("wgmma.mma_async.sync.aligned.m64n64k16.f32.bf16.bf16 {%0, %1, %2, %3, %4, %5, %6, %7, %8, %9, %10, %11, %12, %13, %14, %15, %16, %17, %18, %19, %20, %21, %22, %23, %24, %25, %26, %27, %28, %29, %30, %31}, %32, %33, 1, 1, 1, 0, 0;\n"
      : "+f"(d[0]), "+f"(d[1]), "+f"(d[2]), "+f"(d[3]), "+f"(d[4]), "+f"(d[5]), "+f"(d[6]), "+f"(d[7]), "+f"(d[8]), "+f"(d[9]), "+f"(d[10]), "+f"(d[11]), "+f"(d[12]), "+f"(d[13]), "+f"(d[14]), "+f"(d[15]), "+f"(d[16]), "+f"(d[17]), "+f"(d[18]), "+f"(d[19]), "+f"(d[20]), "+f"(d[21]), "+f"(d[22]), "+f"(d[23]), "+f"(d[24]), "+f"(d[25]), "+f"(d[26]), "+f"(d[27]), "+f"(d[28]), "+f"(d[29]), "+f"(d[30]), "+f"(d[31]) : "l"(da), "l"(db));
}
__device__ __forceinline__ void wgmma64_ss0(float (&d)[32], uint64_t da, uint64_t db) {
  asm volatile("wgmma.mma_async.sync.aligned.m64n64k16.f32.bf16.bf16 {%0, %1, %2, %3, %4, %5, %6, %7, %8, %9, %10, %11, %12, %13, %14, %15, %16, %17, %18, %19, %20, %21, %22, %23, %24, %25, %26, %27, %28, %29, %30, %31}, %32, %33, 0, 1, 1, 0, 0;\n"
      : "=f"(d[0]), "=f"(d[1]), "=f"(d[2]), "=f"(d[3]), "=f"(d[4]), "=f"(d[5]), "=f"(d[6]), "=f"(d[7]), "=f"(d[8]), "=f"(d[9]), "=f"(d[10]), "=f"(d[11]), "=f"(d[12]), "=f"(d[13]), "=f"(d[14]), "=f"(d[15]), "=f"(d[16]), "=f"(d[17]), "=f"(d[18]), "=f"(d[19]), "=f"(d[20]), "=f"(d[21]), "=f"(d[22]), "=f"(d[23]), "=f"(d[24]), "=f"(d[25]), "=f"(d[26]), "=f"(d[27]), "=f"(d[28]), "=f"(d[29]), "=f"(d[30]), "=f"(d[31]) : "l"(da), "l"(db));
}
__device__ __forceinline__ void wgmma128_rs(float (&d)[64], uint32_t a0, uint32_t a1, uint32_t a2, uint32_t a3, uint64_t db) {
  asm volatile("wgmma.mma_async.sync.aligned.m64n128k16.f32.bf16.bf16 {%0, %1, %2, %3, %4, %5, %6, %7, %8, %9, %10, %11, %12, %13, %14, %15, %16, %17, %18, %19, %20, %21, %22, %23, %24, %25, %26, %27, %28, %29, %30, %31, %32, %33, %34, %35, %36, %37, %38, %39, %40, %41, %42, %43, %44, %45, %46, %47, %48, %49, %50, %51, %52, %53, %54, %55, %56, %57, %58, %59, %60, %61, %62, %63}, {%64, %65, %66, %67}, %68, 1, 1, 1, 1;\n"
      : "+f"(d[0]), "+f"(d[1]), "+f"(d[2]), "+f"(d[3]), "+f"(d[4]), "+f"(d[5]), "+f"(d[6]), "+f"(d[7]), "+f"(d[8]), "+f"(d[9]), "+f"(d[10]), "+f"(d[11]), "+f"(d[12]), "+f"(d[13]), "+f"(d[14]), "+f"(d[15]), "+f"(d[16]), "+f"(d[17]), "+f"(d[18]), "+f"(d[19]), "+f"(d[20]), "+f"(d[21]), "+f"(d[22]), "+f"(d[23]), "+f"(d[24]), "+f"(d[25]), "+f"(d[26]), "+f"(d[27]), "+f"(d[28]), "+f"(d[29]), "+f"(d[30]), "+f"(d[31]), "+f"(d[32]), "+f"(d[33]), "+f"(d[34]), "+f"(d[35]), "+f"(d[36]), "+f"(d[37]), "+f"(d[38]), "+f"(d[39]), "+f"(d[40]), "+f"(d[41]), "+f"(d[42]), "+f"(d[43]), "+f"(d[44]), "+f"(d[45]), "+f"(d[46]), "+f"(d[47]), "+f"(d[48]), "+f"(d[49]), "+f"(d[50]), "+f"(d[51]), "+f"(d[52]), "+f"(d[53]), "+f"(d[54]), "+f"(d[55]), "+f"(d[56]), "+f"(d[57]), "+f"(d[58]), "+f"(d[59]), "+f"(d[60]), "+f"(d[61]), "+f"(d[62]), "+f"(d[63]) : "r"(a0), "r"(a1), "r"(a2), "r"(a3), "l"(db));
}
template <int TA, int ACC>
__device__ __forceinline__ void wgmma16(float (&d)[8], uint64_t da, uint64_t db) {
  if (ACC)
    asm volatile("wgmma.mma_async.sync.aligned.m64n16k16.f32.bf16.bf16 {%0, %1, %2, %3, %4, %5, %6, %7}, %8, %9, 1, 1, 1, %10, 0;\n"
      : "+f"(d[0]), "+f"(d[1]), "+f"(d[2]), "+f"(d[3]), "+f"(d[4]), "+f"(d[5]), "+f"(d[6]), "+f"(d[7]) : "l"(da), "l"(db), "n"(TA));
  else
    asm volatile("wgmma.mma_async.sync.aligned.m64n16k16.f32.bf16.bf16 {%0, %1, %2, %3, %4, %5, %6, %7}, %8, %9, 0, 1, 1, %10, 0;\n"
      : "=f"(d[0]), "=f"(d[1]), "=f"(d[2]), "=f"(d[3]), "=f"(d[4]), "=f"(d[5]), "=f"(d[6]), "=f"(d[7]) : "l"(da), "l"(db), "n"(TA));
}
__device__ __forceinline__ uint64_t make_desc_lbo(uint32_t addr, uint32_t lbo) {
  return (uint64_t)((addr & 0x3FFFF) >> 4) | ((uint64_t)(lbo >> 4) << 16) | ((uint64_t)64 << 32) | ((uint64_t)1 << 62);
}
__device__ __forceinline__ void stmatrix_x4(uint32_t addr, uint32_t r0, uint32_t r1, uint32_t r2, uint32_t r3) {
  asm volatile("stmatrix.sync.aligned.m8n8.x4.shared.b16 [%0], {%1, %2, %3, %4};"
               ::"r"(addr), "r"(r0), "r"(r1), "r"(r2), "r"(r3) : "memory");
}

__global__ void __launch_bounds__(512, 1) attn_kernel(const __grid_constant__ Maps maps) {
  extern __shared__ __align__(1024) uint8_t smem[];
  const uint32_t sb = smem_u32(smem);
  const int tid = threadIdx.x;
  const int wg = __shfl_sync(0xffffffffu, tid >> 7, 0);
  const uint32_t bar0 = sb + OFF_BAR;
  auto r_full = [&](int s) { return bar0 + 8 * s; };
  auto r_empty = [&](int s) { return bar0 + 8 * (NSLOT + s); };
  if (tid == 0) {
    for (int s = 0; s < NSLOT; s++) { mbar_init(r_full(s), 1); mbar_init(r_empty(s), 3); }
    asm volatile("fence.mbarrier_init.release.cluster;" ::: "memory");
  }
  __syncthreads();

  if (wg == 3) {
    asm volatile("setmaxnreg.dec.sync.aligned.u32 24;");
    if (tid == 384) {
      int rs = 0, rph = 0;
      for (int item = blockIdx.x; item < 1024; item += gridDim.x) {
        const int br = item >> 9, bh = item & 511, b = bh >> 5, h = bh & 31;
        for (int t = 0; t < 16; t++) {
          mbar_wait(r_empty(rs), rph ^ 1);
          const uint32_t dst = sb + OFF_RING + rs * SLOT_B;
          if (t < 8) {
            mbar_expect_tx(r_full(rs), XW_BYTES);
            tma_load_2d(dst, &maps.x[br], t * 64, b * NQ, r_full(rs));
            tma_load_2d(dst + TILE_B, &maps.wq[br], h * 128, t * 64, r_full(rs));
            tma_load_2d(dst + TILE_B + 8192, &maps.wq[br], h * 128 + 64, t * 64, r_full(rs));
          } else {
            const int u = t - 8;
            const CUtensorMap* mp = (u & 1) ? &maps.v[br] : &maps.k[br];
            const int row = bh * SK + (u >> 1) * 128;
            mbar_expect_tx(r_full(rs), 32768);
            tma_load_2d(dst, mp, 0, row, r_full(rs));
            tma_load_2d(dst + 8192, mp, 0, row + 64, r_full(rs));
            tma_load_2d(dst + 16384, mp, 64, row, r_full(rs));
            tma_load_2d(dst + 24576, mp, 64, row + 64, r_full(rs));
          }
          if (++rs == NSLOT) { rs = 0; rph ^= 1; }
        }
      }
    }
  } else {
    if (wg == 2) {
      asm volatile("setmaxnreg.dec.sync.aligned.u32 72;");
      const int t = tid & 127, warp = t >> 5, lane = t & 31;
      const float cs = 0.08838834764831845f * 1.4426950408889634f;
      float* red = (float*)(smem + OFF_RD);
      const int cq = 2 * (lane & 3);
      int kpos = 0;
      auto stage_of = [&](int pos) { return pos % NSLOT; };
      auto phase_of = [&](int pos) { return (pos / NSLOT) & 1; };
      const int mi = lane >> 3, rr = lane & 7;
      const uint32_t st_off = (uint32_t)((8 * (mi >> 1) + rr) * 128 + (((2 * warp + (mi & 1)) ^ rr) << 4));
      for (int item = blockIdx.x; item < 1024; item += gridDim.x) {
        if (t == 0) {
          for (int p = 0; p < 8; p++) {
            mbar_wait(r_full(stage_of(kpos + p)), phase_of(kpos + p));
            mbar_arrive(r_empty(stage_of(kpos + p)));
          }
        }
        bar_sync(1, 384);
        bar_sync(1, 384);
        float S[8], O0[8], O1[8], m[4], l[4];
#pragma unroll
        for (int i = 0; i < 8; i++) { O0[i] = 0.f; O1[i] = 0.f; }
#pragma unroll
        for (int i = 0; i < 4; i++) { m[i] = -INFINITY; l[i] = 0.f; }
        float SN[8];
        auto issue_S2 = [&](int j) {
          const int pk = kpos + 8 + 2 * (j >> 1);
          mbar_wait(r_full(stage_of(pk)), phase_of(pk));
          const uint32_t kb = sb + OFF_RING + stage_of(pk) * SLOT_B + (j & 1) * 8192;
          const uint32_t qr = sb + OFF_Q + 128 * 128;
          wg_fence();
          wgmma16<0, 0>(SN, make_desc(kb), make_desc(qr));
#pragma unroll
          for (int k = 1; k < 8; k++)
            wgmma16<0, 1>(SN, make_desc(kb + (k >> 2) * 16384 + (k & 3) * 32), make_desc(qr + (k >> 2) * TILE_B + (k & 3) * 32));
          wg_commit();
        };
        issue_S2(0);
        wg_wait<0>();
#pragma unroll 1
        for (int j = 0; j < 8; j++) {
          const int pk = kpos + 8 + 2 * (j >> 1), pv = pk + 1;
#pragma unroll
          for (int i = 0; i < 8; i++) S[i] = SN[i];
          if (t == 0 && (j & 1)) mbar_arrive(r_empty(stage_of(pk)));
          if (j < 7) issue_S2(j + 1);
          float v[4] = {fmaxf(S[0], S[2]), fmaxf(S[1], S[3]), fmaxf(S[4], S[6]), fmaxf(S[5], S[7])};
#pragma unroll
          for (int o = 4; o < 32; o <<= 1) {
#pragma unroll
            for (int e = 0; e < 4; e++) v[e] = fmaxf(v[e], __shfl_xor_sync(0xffffffffu, v[e], o));
          }
          if (lane < 4) {
            *(float2*)(red + warp * 16 + cq) = make_float2(v[0], v[1]);
            *(float2*)(red + warp * 16 + 8 + cq) = make_float2(v[2], v[3]);
          }
          bar_sync(2, 128);
          float al[4];
#pragma unroll
          for (int e = 0; e < 4; e++) {
            const int c = (e >> 1) * 8 + cq + (e & 1);
            const float mm = fmaxf(fmaxf(red[c], red[16 + c]), fmaxf(red[32 + c], red[48 + c]));
            const float mn = fmaxf(m[e], mm);
            al[e] = ex2((m[e] - mn) * cs);
            m[e] = mn;
          }
#pragma unroll
          for (int g = 0; g < 2; g++) {
            const float c0 = -m[2 * g] * cs, c1 = -m[2 * g + 1] * cs;
            S[4 * g] = ex2(fmaf(S[4 * g], cs, c0)); S[4 * g + 1] = ex2(fmaf(S[4 * g + 1], cs, c1));
            S[4 * g + 2] = ex2(fmaf(S[4 * g + 2], cs, c0)); S[4 * g + 3] = ex2(fmaf(S[4 * g + 3], cs, c1));
            l[2 * g] = fmaf(l[2 * g], al[2 * g], S[4 * g] + S[4 * g + 2]);
            l[2 * g + 1] = fmaf(l[2 * g + 1], al[2 * g + 1], S[4 * g + 1] + S[4 * g + 3]);
            O0[4 * g] *= al[2 * g]; O0[4 * g + 1] *= al[2 * g + 1]; O0[4 * g + 2] *= al[2 * g]; O0[4 * g + 3] *= al[2 * g + 1];
            O1[4 * g] *= al[2 * g]; O1[4 * g + 1] *= al[2 * g + 1]; O1[4 * g + 2] *= al[2 * g]; O1[4 * g + 3] *= al[2 * g + 1];
          }
          stmatrix_x4_t(sb + OFF_PR + st_off, pack_bf16(S[0], S[1]), pack_bf16(S[2], S[3]), pack_bf16(S[4], S[5]), pack_bf16(S[6], S[7]));
          fence_async();
          bar_sync(2, 128);
          mbar_wait(r_full(stage_of(pv)), phase_of(pv));
          const uint32_t vb = sb + OFF_RING + stage_of(pv) * SLOT_B + (j & 1) * 8192;
          wg_fence();
#pragma unroll
          for (int k = 0; k < 4; k++) {
            wgmma16<1, 1>(O0, make_desc(vb + k * 2048), make_desc(sb + OFF_PR + k * 32));
            wgmma16<1, 1>(O1, make_desc(vb + 16384 + k * 2048), make_desc(sb + OFF_PR + k * 32));
          }
          wg_commit();
          wg_wait<0>();
          if (t == 0 && (j & 1)) mbar_arrive(r_empty(stage_of(pv)));
        }
#pragma unroll
        for (int o = 4; o < 32; o <<= 1) {
#pragma unroll
          for (int e = 0; e < 4; e++) l[e] += __shfl_xor_sync(0xffffffffu, l[e], o);
        }
        bar_sync(2, 128);
        if (lane < 4) {
          *(float2*)(red + warp * 16 + cq) = make_float2(l[0], l[1]);
          *(float2*)(red + warp * 16 + 8 + cq) = make_float2(l[2], l[3]);
        }
        bar_sync(2, 128);
#pragma unroll
        for (int e = 0; e < 4; e++) {
          const int c = (e >> 1) * 8 + cq + (e & 1);
          l[e] = 1.0f / ((red[c] + red[16 + c]) + (red[32 + c] + red[48 + c]));
        }
        bar_sync(1, 384);
        const uint32_t ob = sb + OFF_Q + 128 * 128 + st_off;
        stmatrix_x4_t(ob, pack_bf16(O0[0] * l[0], O0[1] * l[1]), pack_bf16(O0[2] * l[0], O0[3] * l[1]),
                      pack_bf16(O0[4] * l[2], O0[5] * l[3]), pack_bf16(O0[6] * l[2], O0[7] * l[3]));
        stmatrix_x4_t(ob + TILE_B, pack_bf16(O1[0] * l[0], O1[1] * l[1]), pack_bf16(O1[2] * l[0], O1[3] * l[1]),
                      pack_bf16(O1[4] * l[2], O1[5] * l[3]), pack_bf16(O1[6] * l[2], O1[7] * l[3]));
        fence_async();
        bar_sync(1, 384);
        kpos += 16;
      }
    } else {
    constexpr bool MAIN = true;
    asm volatile("setmaxnreg.inc.sync.aligned.u32 208;");
    const int t = tid & 127, warp = t >> 5, lane = t & 31;
    const float cs = 0.08838834764831845f * 1.4426950408889634f;
    int kpos = 0;
    auto stage_of = [&](int pos) { return pos % NSLOT; };
    auto phase_of = [&](int pos) { return (pos / NSLOT) & 1; };
    if (wg == 1) bar_arrive(4, 256);
    const bool active = MAIN || (warp == 0);

    for (int item = blockIdx.x; item < 1024; item += gridDim.x) {
      const int br = item >> 9, bh = item & 511, b = bh >> 5, h = bh & 31;
      TS(0);
      if (MAIN) {
        float Qa[72];
#pragma unroll
        for (int kc = 0; kc < 8; kc++) {
          const int px = kpos + kc;
          mbar_wait(r_full(stage_of(px)), phase_of(px));
          const uint32_t xb = sb + OFF_RING + stage_of(px) * SLOT_B;
          const uint32_t wb = xb + TILE_B + wg * 8192;
          wg_fence();
          if (kc == 0) wgmma144_0<1>(Qa, make_desc(wb), make_desc(xb));
#pragma unroll
          for (int k = (kc == 0); k < 4; k++) wgmma144<1>(Qa, make_desc(wb + k * 2048), make_desc(xb + k * 32));
          wg_commit();
          if (kc > 0) {
            wg_wait<1>();
            if (t == 0) mbar_arrive(r_empty(stage_of(px - 1)));
          }
        }
        wg_wait<0>();
        if (t == 0) mbar_arrive(r_empty(stage_of(kpos + 7)));
        TS(1);
        if (tid == 0) asm volatile("cp.async.bulk.wait_group.read 0;" ::: "memory");
        bar_sync(1, 384);
        store_acc_T(Qa, sb + OFF_Q + wg * TILE_B, warp, lane);
        fence_async();
      } else {
        if (t == 0) {
          for (int p = 0; p < 8; p++) {
            mbar_wait(r_full(stage_of(kpos + p)), phase_of(kpos + p));
            mbar_arrive(r_empty(stage_of(kpos + p)));
          }
        }
        bar_sync(1, 384);
      }
      bar_sync(1, 384);

      TS(2);
      float SA[32], SB[32], O[64];
#pragma unroll
      for (int i = 0; i < 64; i++) O[i] = 0.f;
      float m0 = -INFINITY, m1 = -INFINITY, l0 = 0.f, l1 = 0.f;
      const uint32_t qb = sb + OFF_Q + wg * 8192;
      auto issue_S = [&](float (&S)[32], int j) {
        const int pk = kpos + 8 + 2 * (j >> 1);
        mbar_wait(r_full(stage_of(pk)), phase_of(pk));
        const uint32_t kb = sb + OFF_RING + stage_of(pk) * SLOT_B + (j & 1) * 8192;
        wg_fence();
        wgmma64_ss0(S, make_desc(qb), make_desc(kb));
#pragma unroll
        for (int k = 1; k < 8; k++)
          wgmma64_ss(S, make_desc(qb + (k >> 2) * TILE_B + (k & 3) * 32), make_desc(kb + (k >> 2) * 16384 + (k & 3) * 32));
        wg_commit();
      };
      auto step = [&](float (&S)[32], int j, bool s_in_flight) {
        bar_sync(4 + wg, 256);
        TS(3 + 3 * j);
        uint32_t P[16];
        float al0 = 1.f, al1 = 1.f;

        if (active) {
          float a0 = S[0], a1 = S[2];
#pragma unroll
          for (int g = 0; g < 8; g++) {
            a0 = fmaxf(a0, fmaxf(S[4 * g], S[4 * g + 1]));
            a1 = fmaxf(a1, fmaxf(S[4 * g + 2], S[4 * g + 3]));
          }
          a0 = fmaxf(a0, __shfl_xor_sync(0xffffffffu, a0, 1));
          a1 = fmaxf(a1, __shfl_xor_sync(0xffffffffu, a1, 1));
          a0 = fmaxf(a0, __shfl_xor_sync(0xffffffffu, a0, 2));
          a1 = fmaxf(a1, __shfl_xor_sync(0xffffffffu, a1, 2));
          const float n0 = fmaxf(m0, a0), n1 = fmaxf(m1, a1);
          al0 = ex2((m0 - n0) * cs); al1 = ex2((m1 - n1) * cs);
          m0 = n0; m1 = n1;
          const float c0 = -n0 * cs, c1 = -n1 * cs;
          float s0 = 0.f, s1 = 0.f;
#pragma unroll
          for (int g = 0; g < 8; g++) {
            const float e0 = ex2(fmaf(S[4 * g], cs, c0)), e1 = ex2(fmaf(S[4 * g + 1], cs, c0));
            const float e2 = ex2(fmaf(S[4 * g + 2], cs, c1)), e3 = ex2(fmaf(S[4 * g + 3], cs, c1));
            s0 += e0 + e1; s1 += e2 + e3;
            P[2 * g] = pack_bf16(e0, e1); P[2 * g + 1] = pack_bf16(e2, e3);
          }
          l0 = fmaf(l0, al0, s0); l1 = fmaf(l1, al1, s1);
        } else {
#pragma unroll
          for (int g = 0; g < 16; g++) P[g] = 0u;
        }
        TS(4 + 3 * j);
        const int pv = kpos + 9 + 2 * (j >> 1);
        mbar_wait(r_full(stage_of(pv)), phase_of(pv));
        TS(5 + 3 * j);
        if (s_in_flight) wg_wait<1>(); else wg_wait<0>();
        if (t == 0 && j > 0 && !(j & 1)) mbar_arrive(r_empty(stage_of(pv - 2)));
#pragma unroll
        for (int g = 0; g < 16; g++) {
          O[4 * g] *= al0; O[4 * g + 1] *= al0; O[4 * g + 2] *= al1; O[4 * g + 3] *= al1;
        }
        const uint32_t vb = sb + OFF_RING + stage_of(pv) * SLOT_B + (j & 1) * 8192;
        wg_fence();
#pragma unroll
        for (int k = 0; k < 4; k++)
          wgmma128_rs(O, P[4 * k], P[4 * k + 1], P[4 * k + 2], P[4 * k + 3], make_desc_lbo(vb + k * 2048, 16384));
        wg_commit();
        bar_arrive(4 + (wg ^ 1), 256);
      };
      if (true) {
        issue_S(SA, 0);
        wg_wait<0>();
#pragma unroll
        for (int jj = 0; jj < 4; jj++) {
          const int j = 2 * jj;
          issue_S(SB, j + 1);
          step(SA, j, true);
          wg_wait<1>();
          if (t == 0) mbar_arrive(r_empty(stage_of(kpos + 8 + 2 * jj)));
          if (jj < 3) {
            issue_S(SA, j + 2);
            step(SB, j + 1, true);
            wg_wait<1>();
          } else {
            step(SB, j + 1, false);
            wg_wait<0>();
          }
        }
      } else {
#pragma unroll 1
        for (int j = 0; j < 8; j++) {
          issue_S(SA, j);
          wg_wait<0>();
          if (t == 0 && (j & 1)) mbar_arrive(r_empty(stage_of(kpos + 8 + (j & ~1))));
          step(SA, j, false);
        }
        wg_wait<0>();
      }
      if (t == 0) mbar_arrive(r_empty(stage_of(kpos + 15)));
      TS(30);
      l0 += __shfl_xor_sync(0xffffffffu, l0, 1); l1 += __shfl_xor_sync(0xffffffffu, l1, 1);
      l0 += __shfl_xor_sync(0xffffffffu, l0, 2); l1 += __shfl_xor_sync(0xffffffffu, l1, 2);
      const float i0 = 1.0f / l0, i1 = 1.0f / l1;
      bar_sync(1, 384);
      TS(31);
      if (active) {
        const int mi = lane >> 3, r = lane & 7;
        const int row = 64 * wg + 16 * warp + (mi & 1) * 8 + r;
#pragma unroll
        for (int g = 0; g < 16; g += 2) {
          const int cg = g + (mi >> 1);
          const uint32_t addr = sb + OFF_Q + (cg >> 3) * TILE_B + row * 128 + (((cg & 7) ^ r) << 4);
          stmatrix_x4(addr, pack_bf16(O[4 * g] * i0, O[4 * g + 1] * i0), pack_bf16(O[4 * g + 2] * i1, O[4 * g + 3] * i1),
                      pack_bf16(O[4 * g + 4] * i0, O[4 * g + 5] * i0), pack_bf16(O[4 * g + 6] * i1, O[4 * g + 7] * i1));
        }
        fence_async();
      }
      bar_sync(1, 384);
      if (tid == 0) {
        tma_store_2d(&maps.os[br], sb + OFF_Q, h * 128, b * NQ);
        tma_store_2d(&maps.os[br], sb + OFF_Q + TILE_B, h * 128 + 64, b * NQ);
        asm volatile("cp.async.bulk.commit_group;" ::: "memory");
      }
      TS(40);
      kpos += 16;
    }
    if (tid == 0) asm volatile("cp.async.bulk.wait_group 0;" ::: "memory");
    }
  }
}

__global__ void __launch_bounds__(384, 1) oproj_kernel(const __grid_constant__ Maps maps) {
  extern __shared__ __align__(1024) uint8_t smem[];
  const uint32_t sb = smem_u32(smem);
  const int tid = threadIdx.x, wg = tid >> 7;
  const uint32_t bar0 = sb + OP_STAGES * XW_BYTES + 2 * TILE_B;
  const int tile = blockIdx.x;
  const int br = tile >> 6, b = (tile >> 2) & 15, nt = tile & 3;
  if (tid == 0) {
    for (int s = 0; s < OP_STAGES; s++) { mbar_init(bar0 + 8 * s, 1); mbar_init(bar0 + 8 * (OP_STAGES + s), 2); }
    asm volatile("fence.mbarrier_init.release.cluster;" ::: "memory");
  }
  __syncthreads();
  if (wg == 2) {
    asm volatile("setmaxnreg.dec.sync.aligned.u32 40;");
    if (tid == 256) {
      int s = 0, ph = 0;
      for (int kc = 0; kc < 64; kc++) {
        mbar_wait(bar0 + 8 * (OP_STAGES + s), ph ^ 1);
        const uint32_t dst = sb + s * XW_BYTES;
        mbar_expect_tx(bar0 + 8 * s, XW_BYTES);
        tma_load_2d(dst, &maps.os[br], kc * 64, b * NQ, bar0 + 8 * s);
        tma_load_2d(dst + TILE_B, &maps.wo[br], nt * 128, kc * 64, bar0 + 8 * s);
        tma_load_2d(dst + TILE_B + 8192, &maps.wo[br], nt * 128 + 64, kc * 64, bar0 + 8 * s);
        if (++s == OP_STAGES) { s = 0; ph ^= 1; }
      }
    }
  } else {
    asm volatile("setmaxnreg.inc.sync.aligned.u32 232;");
    const int t = tid & 127, warp = t >> 5, lane = t & 31;
    float acc[72];
#pragma unroll
    for (int i = 0; i < 72; i++) acc[i] = 0.f;
    int s = 0, ph = 0;
    for (int kc = 0; kc < 64; kc++) {
      mbar_wait(bar0 + 8 * s, ph);
      const uint32_t base = sb + s * XW_BYTES;
      wg_fence();
#pragma unroll
      for (int k = 0; k < 4; k++)
        wgmma144<1>(acc, make_desc(base + TILE_B + wg * 8192 + k * 2048), make_desc(base + k * 32));
      wg_commit();
      wg_wait<1>();
      if (kc > 0 && t == 0) mbar_arrive(bar0 + 8 * (OP_STAGES + (s + OP_STAGES - 1) % OP_STAGES));
      if (++s == OP_STAGES) { s = 0; ph ^= 1; }
    }
    wg_wait<0>();
    const uint32_t ot = sb + OP_STAGES * XW_BYTES + wg * TILE_B;
    store_acc_T(acc, ot, warp, lane);
    fence_async();
    bar_sync(2 + wg, 128);
    if (t == 0) {
      tma_store_2d(&maps.out, ot, br * 512 + nt * 128 + wg * 64, b * NQ);
      asm volatile("cp.async.bulk.commit_group;" ::: "memory");
      asm volatile("cp.async.bulk.wait_group 0;" ::: "memory");
    }
  }
}

typedef CUresult (*EncodeFn)(CUtensorMap*, CUtensorMapDataType, cuuint32_t, void*, const cuuint64_t*,
                             const cuuint64_t*, const cuuint32_t*, const cuuint32_t*, CUtensorMapInterleave,
                             CUtensorMapSwizzle, CUtensorMapL2promotion, CUtensorMapFloatOOBfill);

void encode2d(EncodeFn fn, CUtensorMap* m, const void* ptr, uint64_t cols, uint64_t rows, uint32_t bc, uint32_t brw) {
  cuuint64_t dims[2] = {cols, rows};
  cuuint64_t strides[1] = {cols * 2};
  cuuint32_t box[2] = {bc, brw};
  cuuint32_t es[2] = {1, 1};
  fn(m, CU_TENSOR_MAP_DATA_TYPE_BFLOAT16, 2, const_cast<void*>(ptr), dims, strides, box, es,
     CU_TENSOR_MAP_INTERLEAVE_NONE, CU_TENSOR_MAP_SWIZZLE_128B, CU_TENSOR_MAP_L2_PROMOTION_L2_128B,
     CU_TENSOR_MAP_FLOAT_OOB_FILL_NONE);
}

}

extern "C" void kernel_launch(void* const* d_in, const int* in_sizes, int n_in, void* d_out, int out_size) {
  static Maps maps;
  static bool init = false;
  static void* cached_out = nullptr;
  static void* cached_in0 = nullptr;
  static void* cached_in9 = nullptr;
  if (!init || cached_out != d_out || cached_in0 != d_in[0] || cached_in9 != d_in[6]) {
    void* fp = nullptr;
    cudaDriverEntryPointQueryResult qr;
    cudaGetDriverEntryPoint("cuTensorMapEncodeTiled", &fp, cudaEnableDefault, &qr);
    EncodeFn fn = (EncodeFn)fp;
    void* os = nullptr;
    cudaGetSymbolAddress(&os, g_oscratch);
    for (int br = 0; br < 2; br++) {
      encode2d(fn, &maps.x[br], d_in[5 * br + 0], DM, NROWS, 64, NQ);
      encode2d(fn, &maps.k[br], d_in[5 * br + 1], 128, (uint64_t)NB * NH * SK, 64, 64);
      encode2d(fn, &maps.v[br], d_in[5 * br + 2], 128, (uint64_t)NB * NH * SK, 64, 64);
      encode2d(fn, &maps.wq[br], d_in[5 * br + 3], HD, DM, 64, 64);
      encode2d(fn, &maps.wo[br], d_in[5 * br + 4], DM, HD, 64, 64);
      encode2d(fn, &maps.os[br], (__nv_bfloat16*)os + (size_t)br * NROWS * HD, HD, NROWS, 64, NQ);
    }
    encode2d(fn, &maps.out, d_out, 1024, NROWS, 64, NQ);
    cudaFuncSetAttribute(attn_kernel, cudaFuncAttributeMaxDynamicSharedMemorySize, SMEM_A);
    cudaFuncSetAttribute(oproj_kernel, cudaFuncAttributeMaxDynamicSharedMemorySize, SMEM_B);
    init = true;
    cached_out = d_out;
    cached_in0 = d_in[0];
    cached_in9 = d_in[6];
  }
  attn_kernel<<<132, 512, SMEM_A>>>(maps);
  oproj_kernel<<<128, 384, SMEM_B>>>(maps);
}
```
